```python
import torch

def _softmax(x, axis=-1):
    return torch.softmax(x, dim=axis)
def _gelu(x):
    return torch.nn.functional.gelu(x, approximate="tanh")
def _silu(x):
    return torch.nn.functional.silu(x)
def _sigmoid(x):
    return torch.sigmoid(x)
def _layernorm(x, axis=-1, eps=1e-5):
    m = x.mean(dim=axis, keepdim=True)
    v = x.var(dim=axis, keepdim=True, unbiased=False)
    return (x - m) / torch.sqrt(v + eps)
def _scatter_add(tgt, idx, src, axis=0):
    return tgt.clone().index_add_(axis, idx, src)
def _segment_sum(src, seg, n):
    out = torch.zeros((n,) + src.shape[1:], dtype=src.dtype)
    return out.index_add_(0, seg, src)
def _pad(x, pw):
    flat = tuple(v for pair in reversed(pw) for v in pair)
    return torch.nn.functional.pad(x, flat)

kernel_name = 'sequential_preLN__linear_kernel_hedgehog__dense_activation_relu__prompt'

def setup_inputs():

    _w = (lambda a: (lambda t: t.to(torch.bfloat16) if t.is_floating_point() else t)(torch.as_tensor(a)))
    def _A_setup():
        B, S, D, H = 1, 2048, 640, 32
        Dh = D // H
        return {
            "x": _w((lambda *s: torch.randn(*s, dtype=torch.bfloat16) * 0.05)(B, S, D)),
            "wqkv": _w((lambda *s: torch.randn(*s, dtype=torch.bfloat16) * 0.2)(D, 3 * D)),
            "w_phi": _w((lambda *s: torch.randn(*s, dtype=torch.bfloat16) * 0.2)(H, Dh, Dh) * (Dh ** -0.5)),
            "wo": _w((lambda *s: torch.randn(*s, dtype=torch.bfloat16) * 0.05)(D, D)),
        }
    _A_in = _A_setup()

    def _B_setup():
        B, S, D, Dff = 1, 2048, 640, 1728
        return {
            "x": _w((lambda *s: torch.randn(*s, dtype=torch.bfloat16) * 0.05)(B, S, D)),
            "w1": _w((lambda *s: torch.randn(*s, dtype=torch.bfloat16) * 0.05)(D, Dff)),
            "w2": _w((lambda *s: torch.randn(*s, dtype=torch.bfloat16) * 0.05)(Dff, D)),
        }
    _B_in = _B_setup()

    return {
        "A_x": _A_in["x"],
        "A_wqkv": _A_in["wqkv"],
        "A_w_phi": _A_in["w_phi"],
        "A_wo": _A_in["wo"],
        "B_x": _B_in["x"],
        "B_w1": _B_in["w1"],
        "B_w2": _B_in["w2"],
    }

def reference(A_x, A_wqkv, A_w_phi, A_wo, B_x, B_w1, B_w2):
    def _A_ref(x, wqkv, w_phi, wo):
        B, S, D = x.shape
        H = 32; Dh = D // H
        qkv = (lambda x, *d: x.permute(*d))((x @ wqkv).reshape(B, S, 3, H, Dh), 2, 0, 3, 1, 4)
        q, k, v = qkv[0], qkv[1], qkv[2]
        pq = torch.einsum("bhsd,hdf->bhsf", q, w_phi)
        pk = torch.einsum("bhsd,hdf->bhsf", k, w_phi)
        phi_q = torch.concatenate([_softmax(pq, axis=-1), _softmax(-pq, axis=-1)], axis=-1)
        phi_k = torch.concatenate([_softmax(pk, axis=-1), _softmax(-pk, axis=-1)], axis=-1)
        kv = torch.einsum("bhsf,bhsd->bhfd", phi_k, v)
        z  = torch.einsum("bhsf->bhf", phi_k)
        num = torch.einsum("bhqf,bhfd->bhqd", phi_q, kv)
        den = torch.einsum("bhqf,bhf->bhq", phi_q, z)[..., None] + 1e-6
        o = num / den
        return (lambda x, *d: x.permute(*d))(o, 0, 2, 1, 3).reshape(B, S, D) @ wo

    def _B_ref(x, w1, w2):
        h = torch.einsum("bsd,df->bsf", x, w1)
        zero = torch.zeros_like(h)
        h = torch.maximum(h, zero)
        return torch.einsum("bsf,fd->bsd", h, w2)

    x = A_x
    h = x + _A_ref(_layernorm(x, axis=-1), A_wqkv, A_w_phi, A_wo)
    h2 = h + _B_ref(_layernorm(h, axis=-1), B_w1, B_w2)
    return h2
```

```cpp
#include <cuda_runtime.h>
#include <cuda_bf16.h>
#include <cuda.h>
#include <stdint.h>

namespace {
#define PFTM 0
#define SWP 1
#define HINT "2000"
#define UNRV 1
constexpr int UNR = UNRV;

constexpr int T_S = 2048, T_D = 640, T_FF = 1728;

__device__ __align__(1024) __nv_bfloat16 g_o[T_S * T_D];
__device__ __align__(128) uint4 g_bd[8 * 800];
__device__ __align__(128) float g_kv[8 * 3360];
__device__ __align__(128) float g_sq1[16 * 8 * 128];
__device__ __align__(128) float2 g_st2[8 * T_S];
__device__ __align__(128) float g_cs[8 * 512];
__device__ __align__(128) unsigned g_fcol[8 * 5 * 32];
__device__ __align__(128) unsigned g_frow[16 * 7 * 32];
__device__ unsigned g_started;

#define XPROF(idx) do {} while (0)
#define LPROF(idx) do {} while (0)
#define PROF(idx) do {} while (0)

constexpr int SM_B = 0;
constexpr int SM_A = 131072;
constexpr int SM_X = 196608;
constexpr int SM_Y = 212992;
constexpr int SM_CS1 = SM_Y;
constexpr int SM_CS2 = SM_CS1 + 1024;
constexpr int SM_STP = SM_CS2 + 1024;
constexpr int SM_SQ = SM_STP + 1024;
constexpr int SM_PUB = SM_SQ + 4096;
constexpr int PUB_SQ = SM_PUB, PUB_BD = SM_PUB + 512, PUB_CS = SM_PUB + 1312, PUB_Z = SM_PUB + 2336, PUB_CS2 = 230912;
constexpr int SM_KVP = SM_STP + 512;
constexpr int SM_BAR = 231808;
constexpr int SM_TOTAL = 232448;
constexpr int B_FULLB = 0, B_EMPTYB = 32, B_FULLA = 64, B_EMPTYA = 128, B_CS1 = 192, B_KV = 200, B_CS2 = 208, B_BD = 216, B_HO = 224, B_XR = 232, B_LD = 248, B_RF = 256, B_RE = 288, B_SF = 320, B_SR = 352, B_PHI = 416, B_XA = 424, B_XF = 456, B_WO = 472, B_PEER = 552;

struct Params {
  CUtensorMap x, x16, wq_main, wq_rem, o64, o16, wo, out64, out16, w1_main, w1_half, w2;
};

__device__ __forceinline__ uint32_t smem_u32(const void* p) { return (uint32_t)__cvta_generic_to_shared(p); }
__device__ __forceinline__ uint32_t opaque(uint32_t v) { uint32_t r; asm volatile("mov.u32 %0, %1;" : "=r"(r) : "r"(v)); return r; }
__device__ __forceinline__ void mbar_init(uint32_t bar, uint32_t cnt) { asm volatile("mbarrier.init.shared::cta.b64 [%0], %1;" ::"r"(bar), "r"(cnt)); }
__device__ __forceinline__ void mbar_expect(uint32_t bar, uint32_t bytes) { asm volatile("mbarrier.arrive.expect_tx.shared::cta.b64 _, [%0], %1;" ::"r"(bar), "r"(bytes) : "memory"); }
__device__ __forceinline__ void mbar_arrive(uint32_t bar) { asm volatile("mbarrier.arrive.shared::cta.b64 _, [%0];" ::"r"(bar) : "memory"); }
__device__ __forceinline__ void mbar_wait(uint32_t bar, uint32_t parity) {
  asm volatile(
      "{\n.reg .pred p;\n.reg .u32 c;\n"
      "mbarrier.try_wait.parity.shared::cta.b64 p, [%0], %1;\n"
      "@p bra MW_DONE;\n"
      "mov.u32 c, 0;\n"
      "MW_LOOP:\n"
      "mbarrier.try_wait.parity.shared::cta.b64 p, [%0], %1, " HINT ";\n"
      "@p bra MW_DONE;\n"
      "add.u32 c, c, 1;\n"
      "setp.lt.u32 p, c, 0x400000;\n"
      "@p bra MW_LOOP;\n"
      "trap;\n"
      "MW_DONE:\n}" ::"r"(bar), "r"(parity) : "memory");
}
__device__ __forceinline__ void flag_wait(const unsigned* p, unsigned target) {
  unsigned v; long long t0 = 0; int n = 0;
  while (true) {
    asm volatile("ld.relaxed.gpu.global.u32 %0, [%1];" : "=r"(v) : "l"(p) : "memory");
    if ((int)(v - target) >= 0) break;
    if (++n == 64) { n = 0; long long t = clock64(); if (t0 == 0) t0 = t; else if (t - t0 > 4000000000LL) __trap(); }
  }
}
__device__ __forceinline__ void flag_wait2(const unsigned* p, unsigned tp, const unsigned* q, unsigned tq) {
  unsigned v, u; long long t0 = 0; int n = 0;
  while (true) {
    asm volatile("ld.relaxed.gpu.global.u32 %0, [%2];\nld.relaxed.gpu.global.u32 %1, [%3];" : "=r"(v), "=r"(u) : "l"(p), "l"(q) : "memory");
    if ((int)(v - tp) >= 0 && (int)(u - tq) >= 0) break;
    if (++n == 64) { n = 0; long long t = clock64(); if (t0 == 0) t0 = t; else if (t - t0 > 4000000000LL) __trap(); }
  }
}
__device__ __forceinline__ unsigned ld_relaxed(const unsigned* p) {
  unsigned v; asm volatile("ld.relaxed.gpu.global.u32 %0, [%1];" : "=r"(v) : "l"(p) : "memory"); return v;
}
template <unsigned N> __device__ __forceinline__ unsigned next_target(const unsigned* p) { return (ld_relaxed(p) & ~(N - 1u)) + N; }
__device__ __forceinline__ void bulk_red_f32(void* dst, uint32_t src, uint32_t bytes) {
  asm volatile("cp.reduce.async.bulk.global.shared::cta.bulk_group.add.f32 [%0], [%1], %2;" ::"l"(dst), "r"(src), "r"(bytes) : "memory");
}
__device__ __forceinline__ uint4 lds16(uint32_t a) {
  uint4 v; asm volatile("ld.shared.v4.u32 {%0,%1,%2,%3}, [%4];" : "=r"(v.x), "=r"(v.y), "=r"(v.z), "=r"(v.w) : "r"(a) : "memory"); return v;
}
__device__ __forceinline__ void bulk_s2g(void* dst, uint32_t src, uint32_t bytes) {
  asm volatile("cp.async.bulk.global.shared::cta.bulk_group [%0], [%1], %2;" ::"l"(dst), "r"(src), "r"(bytes) : "memory");
}
__device__ __forceinline__ void flag_add(unsigned* p) { asm volatile("red.relaxed.gpu.global.add.u32 [%0], 1;" ::"l"(p) : "memory"); }
__device__ __forceinline__ void fence_async_smem() { asm volatile("fence.proxy.async.shared::cta;" ::: "memory"); }
__device__ __forceinline__ void fence_async_global() { asm volatile("fence.proxy.async.global;" ::: "memory"); }
__device__ __forceinline__ void tma2d(uint32_t dst, const CUtensorMap* m, uint32_t bar, int c0, int c1) {
  asm volatile("cp.async.bulk.tensor.2d.shared::cluster.global.mbarrier::complete_tx::bytes [%0], [%1, {%3,%4}], [%2];" ::"r"(dst), "l"(m), "r"(bar), "r"(c0), "r"(c1) : "memory");
}
__device__ __forceinline__ void tma3d(uint32_t dst, const CUtensorMap* m, uint32_t bar, int c0, int c1, int c2) {
  asm volatile("cp.async.bulk.tensor.3d.shared::cluster.global.mbarrier::complete_tx::bytes [%0], [%1, {%3,%4,%5}], [%2];" ::"r"(dst), "l"(m), "r"(bar), "r"(c0), "r"(c1), "r"(c2) : "memory");
}
__device__ __forceinline__ void tma_st2d(const CUtensorMap* m, uint32_t src, int c0, int c1) {
  asm volatile("cp.async.bulk.tensor.2d.global.shared::cta.bulk_group [%0, {%2,%3}], [%1];" ::"l"(m), "r"(src), "r"(c0), "r"(c1) : "memory");
}
__device__ __forceinline__ void tma_red2d(const CUtensorMap* m, uint32_t src, int c0, int c1) {
  asm volatile("cp.reduce.async.bulk.tensor.2d.global.shared::cta.add.bulk_group [%0, {%2,%3}], [%1];" ::"l"(m), "r"(src), "r"(c0), "r"(c1) : "memory");
}
__device__ __forceinline__ uint32_t map_peer(uint32_t a, uint32_t rank) {
  uint32_t r; asm("mapa.shared::cluster.u32 %0, %1, %2;" : "=r"(r) : "r"(a), "r"(rank)); return r;
}
__device__ __forceinline__ void cluster_arrive_relaxed() { asm volatile("barrier.cluster.arrive.relaxed.aligned;" ::: "memory"); }
__device__ __forceinline__ void cluster_wait() { asm volatile("barrier.cluster.wait.acquire.aligned;" ::: "memory"); }
__device__ __forceinline__ void bulk_commit() { asm volatile("cp.async.bulk.commit_group;" ::: "memory"); }
template <int N> __device__ __forceinline__ void bulk_wait() { asm volatile("cp.async.bulk.wait_group %0;" ::"n"(N) : "memory"); }
template <int N> __device__ __forceinline__ void bulk_wait_read() { asm volatile("cp.async.bulk.wait_group.read %0;" ::"n"(N) : "memory"); }
__device__ __forceinline__ void bar_sync(int id, int n) { asm volatile("bar.sync %0, %1;" ::"r"(id), "r"(n) : "memory"); }
__device__ __forceinline__ void bar_arrive(int id, int n) { asm volatile("bar.arrive %0, %1;" ::"r"(id), "r"(n) : "memory"); }
constexpr uint32_t SB0 = 1024;
__host__ __device__ constexpr uint32_t dlo(uint32_t off, uint32_t lbo) { return ((SB0 + off) >> 4) | ((lbo >> 4) << 16); }
__host__ __device__ constexpr uint32_t dhi(uint32_t sbo, uint32_t swz) { return (sbo >> 4) | (swz << 30); }
constexpr uint32_t H128 = dhi(1024, 1), H32 = dhi(256, 3);
__device__ __forceinline__ void wg_fence() { asm volatile("wgmma.fence.sync.aligned;" ::: "memory"); }
__device__ __forceinline__ void wg_commit() { asm volatile("wgmma.commit_group.sync.aligned;" ::: "memory"); }
template <int N> __device__ __forceinline__ void wg_wait() { asm volatile("wgmma.wait_group.sync.aligned %0;" ::"n"(N) : "memory"); }
template <int N> __device__ __forceinline__ void reg_fence(float (&d)[N]) {
#pragma unroll
  for (int i = 0; i < N; i++) asm volatile("" : "+f"(d[i])::"memory");
}
__device__ __forceinline__ uint32_t pack2(float lo, float hi) {
  uint32_t r; asm("cvt.rn.bf16x2.f32 %0, %1, %2;" : "=r"(r) : "f"(hi), "f"(lo)); return r;
}
__device__ __forceinline__ uint32_t pack2_relu(float lo, float hi) {
  uint32_t r; asm("cvt.rn.relu.bf16x2.f32 %0, %1, %2;" : "=r"(r) : "f"(hi), "f"(lo)); return r;
}
__device__ __forceinline__ float bf_lo(uint32_t v) { return __uint_as_float(v << 16); }
__device__ __forceinline__ float bf_hi(uint32_t v) { return __uint_as_float(v & 0xffff0000u); }
__device__ __forceinline__ uint32_t badd2(uint32_t a, uint32_t b) { uint32_t r; asm("add.rn.bf16x2 %0, %1, %2;" : "=r"(r) : "r"(a), "r"(b)); return r; }
__device__ __forceinline__ float ex2(float x) { float r; asm("ex2.approx.ftz.f32 %0, %1;" : "=f"(r) : "f"(x)); return r; }
__device__ __forceinline__ float rcp(float x) { float r; asm("rcp.approx.ftz.f32 %0, %1;" : "=f"(r) : "f"(x)); return r; }
__device__ __forceinline__ void stsm4(uint32_t a, uint32_t r0, uint32_t r1, uint32_t r2, uint32_t r3) {
  asm volatile("stmatrix.sync.aligned.m8n8.x4.shared.b16 [%0], {%1,%2,%3,%4};" ::"r"(a), "r"(r0), "r"(r1), "r"(r2), "r"(r3) : "memory");
}
__device__ __forceinline__ void bulk_g2s(uint32_t dst, const void* src, uint32_t bytes, uint32_t bar) {
  asm volatile("cp.async.bulk.shared::cluster.global.mbarrier::complete_tx::bytes [%0], [%1], %2, [%3];" ::"r"(dst), "l"(src), "r"(bytes), "r"(bar) : "memory");
}
__device__ __forceinline__ void acc8(float (&s)[8], uint4 v) {
  s[0] += bf_lo(v.x); s[1] += bf_hi(v.x); s[2] += bf_lo(v.y); s[3] += bf_hi(v.y);
  s[4] += bf_lo(v.z); s[5] += bf_hi(v.z); s[6] += bf_lo(v.w); s[7] += bf_hi(v.w);
}

template <uint32_t HA, uint32_t HB>
__device__ __forceinline__ void wgmma_ss_n192_t01(float (&d)[96], uint32_t la, uint32_t lb, int sd) {
  asm volatile("{\n.reg .pred p;\n.reg .b64 da, db;\nsetp.ne.b32 p, %98, 0;\nmov.b64 da, {%96, %99};\nmov.b64 db, {%97, %100};\n"
    "wgmma.mma_async.sync.aligned.m64n192k16.f32.bf16.bf16 {%0, %1, %2, %3, %4, %5, %6, %7, %8, %9, %10, %11, %12, %13, %14, %15, %16, %17, %18, %19, %20, %21, %22, %23, %24, %25, %26, %27, %28, %29, %30, %31, %32, %33, %34, %35, %36, %37, %38, %39, %40, %41, %42, %43, %44, %45, %46, %47, %48, %49, %50, %51, %52, %53, %54, %55, %56, %57, %58, %59, %60, %61, %62, %63, %64, %65, %66, %67, %68, %69, %70, %71, %72, %73, %74, %75, %76, %77, %78, %79, %80, %81, %82, %83, %84, %85, %86, %87, %88, %89, %90, %91, %92, %93, %94, %95}, da, db, p, 1, 1, 0, 1;\n}\n"
    : "+f"(d[0]), "+f"(d[1]), "+f"(d[2]), "+f"(d[3]), "+f"(d[4]), "+f"(d[5]), "+f"(d[6]), "+f"(d[7]), "+f"(d[8]), "+f"(d[9]), "+f"(d[10]), "+f"(d[11]), "+f"(d[12]), "+f"(d[13]), "+f"(d[14]), "+f"(d[15]), "+f"(d[16]), "+f"(d[17]), "+f"(d[18]), "+f"(d[19]), "+f"(d[20]), "+f"(d[21]), "+f"(d[22]), "+f"(d[23]), "+f"(d[24]), "+f"(d[25]), "+f"(d[26]), "+f"(d[27]), "+f"(d[28]), "+f"(d[29]), "+f"(d[30]), "+f"(d[31]), "+f"(d[32]), "+f"(d[33]), "+f"(d[34]), "+f"(d[35]), "+f"(d[36]), "+f"(d[37]), "+f"(d[38]), "+f"(d[39]), "+f"(d[40]), "+f"(d[41]), "+f"(d[42]), "+f"(d[43]), "+f"(d[44]), "+f"(d[45]), "+f"(d[46]), "+f"(d[47]), "+f"(d[48]), "+f"(d[49]), "+f"(d[50]), "+f"(d[51]), "+f"(d[52]), "+f"(d[53]), "+f"(d[54]), "+f"(d[55]), "+f"(d[56]), "+f"(d[57]), "+f"(d[58]), "+f"(d[59]), "+f"(d[60]), "+f"(d[61]), "+f"(d[62]), "+f"(d[63]), "+f"(d[64]), "+f"(d[65]), "+f"(d[66]), "+f"(d[67]), "+f"(d[68]), "+f"(d[69]), "+f"(d[70]), "+f"(d[71]), "+f"(d[72]), "+f"(d[73]), "+f"(d[74]), "+f"(d[75]), "+f"(d[76]), "+f"(d[77]), "+f"(d[78]), "+f"(d[79]), "+f"(d[80]), "+f"(d[81]), "+f"(d[82]), "+f"(d[83]), "+f"(d[84]), "+f"(d[85]), "+f"(d[86]), "+f"(d[87]), "+f"(d[88]), "+f"(d[89]), "+f"(d[90]), "+f"(d[91]), "+f"(d[92]), "+f"(d[93]), "+f"(d[94]), "+f"(d[95])
    : "r"(la), "r"(lb), "r"(sd), "n"(HA), "n"(HB));
}
template <uint32_t HA, uint32_t HB>
__device__ __forceinline__ void wgmma_ss_n56_t01(float (&d)[28], uint32_t la, uint32_t lb, int sd) {
  asm volatile("{\n.reg .pred p;\n.reg .b64 da, db;\nsetp.ne.b32 p, %30, 0;\nmov.b64 da, {%28, %31};\nmov.b64 db, {%29, %32};\n"
    "wgmma.mma_async.sync.aligned.m64n56k16.f32.bf16.bf16 {%0, %1, %2, %3, %4, %5, %6, %7, %8, %9, %10, %11, %12, %13, %14, %15, %16, %17, %18, %19, %20, %21, %22, %23, %24, %25, %26, %27}, da, db, p, 1, 1, 0, 1;\n}\n"
    : "+f"(d[0]), "+f"(d[1]), "+f"(d[2]), "+f"(d[3]), "+f"(d[4]), "+f"(d[5]), "+f"(d[6]), "+f"(d[7]), "+f"(d[8]), "+f"(d[9]), "+f"(d[10]), "+f"(d[11]), "+f"(d[12]), "+f"(d[13]), "+f"(d[14]), "+f"(d[15]), "+f"(d[16]), "+f"(d[17]), "+f"(d[18]), "+f"(d[19]), "+f"(d[20]), "+f"(d[21]), "+f"(d[22]), "+f"(d[23]), "+f"(d[24]), "+f"(d[25]), "+f"(d[26]), "+f"(d[27])
    : "r"(la), "r"(lb), "r"(sd), "n"(HA), "n"(HB));
}
template <uint32_t HB>
__device__ __forceinline__ void wgmma_rs_n80_t0(float (&d)[40], uint32_t a0, uint32_t a1, uint32_t a2, uint32_t a3, uint32_t lb, int sd) {
  asm volatile("{\n.reg .pred p;\n.reg .b64 db;\nsetp.ne.b32 p, %45, 0;\nmov.b64 db, {%44, %46};\n"
    "wgmma.mma_async.sync.aligned.m64n80k16.f32.bf16.bf16 {%0, %1, %2, %3, %4, %5, %6, %7, %8, %9, %10, %11, %12, %13, %14, %15, %16, %17, %18, %19, %20, %21, %22, %23, %24, %25, %26, %27, %28, %29, %30, %31, %32, %33, %34, %35, %36, %37, %38, %39}, {%40, %41, %42, %43}, db, p, 1, 1, 0;\n}\n"
    : "+f"(d[0]), "+f"(d[1]), "+f"(d[2]), "+f"(d[3]), "+f"(d[4]), "+f"(d[5]), "+f"(d[6]), "+f"(d[7]), "+f"(d[8]), "+f"(d[9]), "+f"(d[10]), "+f"(d[11]), "+f"(d[12]), "+f"(d[13]), "+f"(d[14]), "+f"(d[15]), "+f"(d[16]), "+f"(d[17]), "+f"(d[18]), "+f"(d[19]), "+f"(d[20]), "+f"(d[21]), "+f"(d[22]), "+f"(d[23]), "+f"(d[24]), "+f"(d[25]), "+f"(d[26]), "+f"(d[27]), "+f"(d[28]), "+f"(d[29]), "+f"(d[30]), "+f"(d[31]), "+f"(d[32]), "+f"(d[33]), "+f"(d[34]), "+f"(d[35]), "+f"(d[36]), "+f"(d[37]), "+f"(d[38]), "+f"(d[39])
    : "r"(a0), "r"(a1), "r"(a2), "r"(a3), "r"(lb), "r"(sd), "n"(HB));
}
template <uint32_t HA, uint32_t HB>
__device__ __forceinline__ void wgmma_ss_n80_t11(float (&d)[40], uint32_t la, uint32_t lb, int sd) {
  asm volatile("{\n.reg .pred p;\n.reg .b64 da, db;\nsetp.ne.b32 p, %42, 0;\nmov.b64 da, {%40, %43};\nmov.b64 db, {%41, %44};\n"
    "wgmma.mma_async.sync.aligned.m64n80k16.f32.bf16.bf16 {%0, %1, %2, %3, %4, %5, %6, %7, %8, %9, %10, %11, %12, %13, %14, %15, %16, %17, %18, %19, %20, %21, %22, %23, %24, %25, %26, %27, %28, %29, %30, %31, %32, %33, %34, %35, %36, %37, %38, %39}, da, db, p, 1, 1, 1, 1;\n}\n"
    : "+f"(d[0]), "+f"(d[1]), "+f"(d[2]), "+f"(d[3]), "+f"(d[4]), "+f"(d[5]), "+f"(d[6]), "+f"(d[7]), "+f"(d[8]), "+f"(d[9]), "+f"(d[10]), "+f"(d[11]), "+f"(d[12]), "+f"(d[13]), "+f"(d[14]), "+f"(d[15]), "+f"(d[16]), "+f"(d[17]), "+f"(d[18]), "+f"(d[19]), "+f"(d[20]), "+f"(d[21]), "+f"(d[22]), "+f"(d[23]), "+f"(d[24]), "+f"(d[25]), "+f"(d[26]), "+f"(d[27]), "+f"(d[28]), "+f"(d[29]), "+f"(d[30]), "+f"(d[31]), "+f"(d[32]), "+f"(d[33]), "+f"(d[34]), "+f"(d[35]), "+f"(d[36]), "+f"(d[37]), "+f"(d[38]), "+f"(d[39])
    : "r"(la), "r"(lb), "r"(sd), "n"(HA), "n"(HB));
}
template <uint32_t HA, uint32_t HB>
__device__ __forceinline__ void wgmma_ss_n48_t00(float (&d)[24], uint32_t la, uint32_t lb, int sd) {
  asm volatile("{\n.reg .pred p;\n.reg .b64 da, db;\nsetp.ne.b32 p, %26, 0;\nmov.b64 da, {%24, %27};\nmov.b64 db, {%25, %28};\n"
    "wgmma.mma_async.sync.aligned.m64n48k16.f32.bf16.bf16 {%0, %1, %2, %3, %4, %5, %6, %7, %8, %9, %10, %11, %12, %13, %14, %15, %16, %17, %18, %19, %20, %21, %22, %23}, da, db, p, 1, 1, 0, 0;\n}\n"
    : "+f"(d[0]), "+f"(d[1]), "+f"(d[2]), "+f"(d[3]), "+f"(d[4]), "+f"(d[5]), "+f"(d[6]), "+f"(d[7]), "+f"(d[8]), "+f"(d[9]), "+f"(d[10]), "+f"(d[11]), "+f"(d[12]), "+f"(d[13]), "+f"(d[14]), "+f"(d[15]), "+f"(d[16]), "+f"(d[17]), "+f"(d[18]), "+f"(d[19]), "+f"(d[20]), "+f"(d[21]), "+f"(d[22]), "+f"(d[23])
    : "r"(la), "r"(lb), "r"(sd), "n"(HA), "n"(HB));
}
template <uint32_t HA, uint32_t HB>
__device__ __forceinline__ void wgmma_ss_n80_t01(float (&d)[40], uint32_t la, uint32_t lb, int sd) {
  asm volatile("{\n.reg .pred p;\n.reg .b64 da, db;\nsetp.ne.b32 p, %42, 0;\nmov.b64 da, {%40, %43};\nmov.b64 db, {%41, %44};\n"
    "wgmma.mma_async.sync.aligned.m64n80k16.f32.bf16.bf16 {%0, %1, %2, %3, %4, %5, %6, %7, %8, %9, %10, %11, %12, %13, %14, %15, %16, %17, %18, %19, %20, %21, %22, %23, %24, %25, %26, %27, %28, %29, %30, %31, %32, %33, %34, %35, %36, %37, %38, %39}, da, db, p, 1, 1, 0, 1;\n}\n"
    : "+f"(d[0]), "+f"(d[1]), "+f"(d[2]), "+f"(d[3]), "+f"(d[4]), "+f"(d[5]), "+f"(d[6]), "+f"(d[7]), "+f"(d[8]), "+f"(d[9]), "+f"(d[10]), "+f"(d[11]), "+f"(d[12]), "+f"(d[13]), "+f"(d[14]), "+f"(d[15]), "+f"(d[16]), "+f"(d[17]), "+f"(d[18]), "+f"(d[19]), "+f"(d[20]), "+f"(d[21]), "+f"(d[22]), "+f"(d[23]), "+f"(d[24]), "+f"(d[25]), "+f"(d[26]), "+f"(d[27]), "+f"(d[28]), "+f"(d[29]), "+f"(d[30]), "+f"(d[31]), "+f"(d[32]), "+f"(d[33]), "+f"(d[34]), "+f"(d[35]), "+f"(d[36]), "+f"(d[37]), "+f"(d[38]), "+f"(d[39])
    : "r"(la), "r"(lb), "r"(sd), "n"(HA), "n"(HB));
}
template <uint32_t HA, uint32_t HB>
__device__ __forceinline__ void wgmma_ss_n224_t01(float (&d)[112], uint32_t la, uint32_t lb, int sd) {
  asm volatile("{\n.reg .pred p;\n.reg .b64 da, db;\nsetp.ne.b32 p, %114, 0;\nmov.b64 da, {%112, %115};\nmov.b64 db, {%113, %116};\n"
    "wgmma.mma_async.sync.aligned.m64n224k16.f32.bf16.bf16 {%0, %1, %2, %3, %4, %5, %6, %7, %8, %9, %10, %11, %12, %13, %14, %15, %16, %17, %18, %19, %20, %21, %22, %23, %24, %25, %26, %27, %28, %29, %30, %31, %32, %33, %34, %35, %36, %37, %38, %39, %40, %41, %42, %43, %44, %45, %46, %47, %48, %49, %50, %51, %52, %53, %54, %55, %56, %57, %58, %59, %60, %61, %62, %63, %64, %65, %66, %67, %68, %69, %70, %71, %72, %73, %74, %75, %76, %77, %78, %79, %80, %81, %82, %83, %84, %85, %86, %87, %88, %89, %90, %91, %92, %93, %94, %95, %96, %97, %98, %99, %100, %101, %102, %103, %104, %105, %106, %107, %108, %109, %110, %111}, da, db, p, 1, 1, 0, 1;\n}\n"
    : "+f"(d[0]), "+f"(d[1]), "+f"(d[2]), "+f"(d[3]), "+f"(d[4]), "+f"(d[5]), "+f"(d[6]), "+f"(d[7]), "+f"(d[8]), "+f"(d[9]), "+f"(d[10]), "+f"(d[11]), "+f"(d[12]), "+f"(d[13]), "+f"(d[14]), "+f"(d[15]), "+f"(d[16]), "+f"(d[17]), "+f"(d[18]), "+f"(d[19]), "+f"(d[20]), "+f"(d[21]), "+f"(d[22]), "+f"(d[23]), "+f"(d[24]), "+f"(d[25]), "+f"(d[26]), "+f"(d[27]), "+f"(d[28]), "+f"(d[29]), "+f"(d[30]), "+f"(d[31]), "+f"(d[32]), "+f"(d[33]), "+f"(d[34]), "+f"(d[35]), "+f"(d[36]), "+f"(d[37]), "+f"(d[38]), "+f"(d[39]), "+f"(d[40]), "+f"(d[41]), "+f"(d[42]), "+f"(d[43]), "+f"(d[44]), "+f"(d[45]), "+f"(d[46]), "+f"(d[47]), "+f"(d[48]), "+f"(d[49]), "+f"(d[50]), "+f"(d[51]), "+f"(d[52]), "+f"(d[53]), "+f"(d[54]), "+f"(d[55]), "+f"(d[56]), "+f"(d[57]), "+f"(d[58]), "+f"(d[59]), "+f"(d[60]), "+f"(d[61]), "+f"(d[62]), "+f"(d[63]), "+f"(d[64]), "+f"(d[65]), "+f"(d[66]), "+f"(d[67]), "+f"(d[68]), "+f"(d[69]), "+f"(d[70]), "+f"(d[71]), "+f"(d[72]), "+f"(d[73]), "+f"(d[74]), "+f"(d[75]), "+f"(d[76]), "+f"(d[77]), "+f"(d[78]), "+f"(d[79]), "+f"(d[80]), "+f"(d[81]), "+f"(d[82]), "+f"(d[83]), "+f"(d[84]), "+f"(d[85]), "+f"(d[86]), "+f"(d[87]), "+f"(d[88]), "+f"(d[89]), "+f"(d[90]), "+f"(d[91]), "+f"(d[92]), "+f"(d[93]), "+f"(d[94]), "+f"(d[95]), "+f"(d[96]), "+f"(d[97]), "+f"(d[98]), "+f"(d[99]), "+f"(d[100]), "+f"(d[101]), "+f"(d[102]), "+f"(d[103]), "+f"(d[104]), "+f"(d[105]), "+f"(d[106]), "+f"(d[107]), "+f"(d[108]), "+f"(d[109]), "+f"(d[110]), "+f"(d[111])
    : "r"(la), "r"(lb), "r"(sd), "n"(HA), "n"(HB));
}
template <uint32_t HB>
__device__ __forceinline__ void wgmma_rs_n64_t1(float (&d)[32], uint32_t a0, uint32_t a1, uint32_t a2, uint32_t a3, uint32_t lb, int sd) {
  asm volatile("{\n.reg .pred p;\n.reg .b64 db;\nsetp.ne.b32 p, %37, 0;\nmov.b64 db, {%36, %38};\n"
    "wgmma.mma_async.sync.aligned.m64n64k16.f32.bf16.bf16 {%0, %1, %2, %3, %4, %5, %6, %7, %8, %9, %10, %11, %12, %13, %14, %15, %16, %17, %18, %19, %20, %21, %22, %23, %24, %25, %26, %27, %28, %29, %30, %31}, {%32, %33, %34, %35}, db, p, 1, 1, 1;\n}\n"
    : "+f"(d[0]), "+f"(d[1]), "+f"(d[2]), "+f"(d[3]), "+f"(d[4]), "+f"(d[5]), "+f"(d[6]), "+f"(d[7]), "+f"(d[8]), "+f"(d[9]), "+f"(d[10]), "+f"(d[11]), "+f"(d[12]), "+f"(d[13]), "+f"(d[14]), "+f"(d[15]), "+f"(d[16]), "+f"(d[17]), "+f"(d[18]), "+f"(d[19]), "+f"(d[20]), "+f"(d[21]), "+f"(d[22]), "+f"(d[23]), "+f"(d[24]), "+f"(d[25]), "+f"(d[26]), "+f"(d[27]), "+f"(d[28]), "+f"(d[29]), "+f"(d[30]), "+f"(d[31])
    : "r"(a0), "r"(a1), "r"(a2), "r"(a3), "r"(lb), "r"(sd), "n"(HB));
}

template <int R>
__device__ __forceinline__ float dual_softmax(const float (&p)[40], float sc, uint32_t dst) {
  float mx = fmaxf(p[2 * R], p[2 * R + 1]), mn = fminf(p[2 * R], p[2 * R + 1]);
#pragma unroll
  for (int t = 1; t < 10; t++) {
    mx = fmaxf(mx, fmaxf(p[4 * t + 2 * R], p[4 * t + 2 * R + 1]));
    mn = fminf(mn, fminf(p[4 * t + 2 * R], p[4 * t + 2 * R + 1]));
  }
  mx *= -sc; mn *= sc;
  float e[40];
#pragma unroll
  for (int t = 0; t < 10; t++) {
    e[2 * t] = ex2(fmaf(p[4 * t + 2 * R], sc, mx)); e[2 * t + 1] = ex2(fmaf(p[4 * t + 2 * R + 1], sc, mx));
    e[20 + 2 * t] = ex2(fmaf(p[4 * t + 2 * R], -sc, mn)); e[21 + 2 * t] = ex2(fmaf(p[4 * t + 2 * R + 1], -sc, mn));
  }
  float s0 = e[0] + e[1], s1 = e[2] + e[3], s2 = e[20] + e[21], s3 = e[22] + e[23];
#pragma unroll
  for (int t = 4; t < 20; t += 2) { s0 += e[t]; s1 += e[t + 1]; s2 += e[20 + t]; s3 += e[21 + t]; }
  const float rp = rcp(s0 + s1), rn = rcp(s2 + s3);
#pragma unroll
  for (int c = 0; c < 5; c++) {
    uint32_t u[4];
#pragma unroll
    for (int i = 0; i < 4; i++) { const int f = 8 * c + 2 * i; const float r = f < 20 ? rp : rn; u[i] = pack2(e[f] * r, e[f + 1] * r); }
    asm volatile("st.shared.v4.b32 [%0], {%1,%2,%3,%4};" ::"r"(dst + c * 1056), "r"(u[0]), "r"(u[1]), "r"(u[2]), "r"(u[3]) : "memory");
  }
  return e[39];
}

__device__ __forceinline__ void stage80(uint32_t base, uint32_t rem, const uint32_t (&v)[20], int w, int lane) {
  const int row = w * 16 + ((lane >> 3) & 1) * 8 + (lane & 7), hi = lane >> 4;
#pragma unroll
  for (int T = 0; T < 8; T += 2) stsm4(base + row * 128 + (((T + hi) ^ (row & 7)) << 4), v[2 * T], v[2 * T + 1], v[2 * T + 2], v[2 * T + 3]);
  stsm4(rem + row * 32 + ((hi ^ ((row >> 2) & 1)) << 4), v[16], v[17], v[18], v[19]);
}

__device__ __forceinline__ void load80(uint32_t main_, uint32_t rem, uint32_t (&v)[20], int w, int lane) {
  const int row = w * 16 + ((lane >> 3) & 1) * 8 + (lane & 7), hi = lane >> 4;
#pragma unroll
  for (int T = 0; T < 10; T += 2) {
    const uint32_t a = T < 8 ? main_ + row * 128 + (((T + hi) ^ (row & 7)) << 4) : rem + row * 32 + ((hi ^ ((row >> 2) & 1)) << 4);
    asm volatile("ldmatrix.sync.aligned.m8n8.x4.shared.b16 {%0,%1,%2,%3}, [%4];" : "=r"(v[2 * T]), "=r"(v[2 * T + 1]), "=r"(v[2 * T + 2]), "=r"(v[2 * T + 3]) : "r"(a) : "memory");
  }
}

__device__ __forceinline__ float col_reduce8(const float (&s)[8], int lane) {
  float t[4], u[2];
  const bool b4 = lane & 16, b3 = lane & 8, b2 = lane & 4;
#pragma unroll
  for (int i = 0; i < 4; i++) t[i] = (b4 ? s[4 + i] : s[i]) + __shfl_xor_sync(0xffffffffu, b4 ? s[i] : s[4 + i], 16);
#pragma unroll
  for (int i = 0; i < 2; i++) u[i] = (b3 ? t[2 + i] : t[i]) + __shfl_xor_sync(0xffffffffu, b3 ? t[i] : t[2 + i], 8);
  return (b2 ? u[1] : u[0]) + __shfl_xor_sync(0xffffffffu, b2 ? u[0] : u[1], 4);
}

template <bool kMap>
__global__ void __launch_bounds__(384, 1)
fused_block_kernel(const __grid_constant__ Params P, const __nv_bfloat16* __restrict__ wphi,
                   const __nv_bfloat16* __restrict__ wo, const __nv_bfloat16* __restrict__ w1, const __nv_bfloat16* __restrict__ w2) {
  extern __shared__ __align__(1024) unsigned char smem[];
  const uint32_t sb = smem_u32(smem);
  const int tid = threadIdx.x;

  int gp, sec, rk;
  if (kMap) {
    uint32_t smid, nsm;
    asm("mov.u32 %0, %%smid;" : "=r"(smid));
    asm("mov.u32 %0, %%nsmid;" : "=r"(nsm));
    const int s = nsm == 132 ? (int)smid : (int)blockIdx.x, u = (s - 64) >> 1, q = (u * 37) >> 8;
    sec = s >= 64;
    gp = s < 64 ? (s >> 1) & 7 : (s >= 120 ? 0 : u - 7 * q + 1);
    rk = s < 64 ? (s >> 4) * 2 + (s & 1) : (s >= 120 ? s - 124 : 2 * q + (s & 1));
    if (rk < 0) {
      if (tid == 0) {
        atomicInc(&g_started, 131);
        long long t0 = clock64();
        while (*(volatile unsigned*)&g_started != 0) { __nanosleep(200); if (clock64() - t0 > 4000000000LL) __trap(); }
      }
      return;
    }
  } else {
    gp = (blockIdx.x >> 3) & 7; sec = blockIdx.x >> 6; rk = blockIdx.x & 7;
  }
  const int ti = 8 * (gp >> 2) + 4 * sec + (rk >> 1), tj = 2 * (gp & 3) + (rk & 1), tile = ti * 8 + tj;
  const int rot = (((gp >> 2) ^ gp) & 1) * 5;
  const int cs_u = ti & 7, sq_v = (gp & 2) | (tj & 1);
  const uint32_t bars = sb + SM_BAR;
  if (tid == 256) {
    mbar_init(bars + B_FULLB, 1); mbar_init(bars + B_FULLA, 1); mbar_init(bars + B_FULLA + 32, 1);
    asm volatile("fence.mbarrier_init.release.cluster;" ::: "memory");
    mbar_expect(bars + B_FULLB, 30720);
    tma3d(sb + SM_B, &P.wq_main, bars + B_FULLB, tj * 80, rot * 64, 0);
    mbar_expect(bars + B_FULLA, 8192);
    tma2d(sb + SM_A, &P.x, bars + B_FULLA, rot * 64, ti * 128);
    mbar_expect(bars + B_FULLA + 32, 8192);
    tma2d(sb + SM_A + 32768, &P.x, bars + B_FULLA + 32, rot * 64, ti * 128 + 64);
    tma3d(sb + SM_B + 24576, &P.wq_rem, bars + B_FULLB, tj * 80 + 64, rot * 64, 0);
    PROF(50);
#pragma unroll
    for (int n = 1; n < 4; n++) { mbar_init(bars + B_FULLB + n * 8, 1); mbar_init(bars + B_FULLA + n * 8, 1); mbar_init(bars + B_FULLA + 32 + n * 8, 1); }
    asm volatile("fence.mbarrier_init.release.cluster;" ::: "memory");
  }
  const int wid = __shfl_sync(0xffffffffu, tid >> 5, 0);
  const int wg = wid >> 2, w = wid & 3, lane = tid & 31;
  if (tid == 352) {
#pragma unroll
    for (int b = 4; b < 69; b++)
      if (b < 8 || b >= 16) mbar_init(bars + b * 8, ((b >= 44 && b < 52) || (b >= 36 && b < 40) || b == 57 || b == 58) ? 4 : (b < 8 ? 2 : 1));
    asm volatile("fence.mbarrier_init.release.cluster;" ::: "memory");
  }
  uint32_t peer;
  asm("mov.u32 %0, %%cluster_ctarank;" : "=r"(peer));
  peer ^= 1u;
  if (tid == 288) {
    *reinterpret_cast<volatile int*>(smem + SM_BAR + B_PEER) = tile;
    asm volatile("fence.release.sync_restrict::shared::cta.cluster;" ::: "memory");
  }
  __syncwarp();
  if (wid == 8 || wid == 11) bar_arrive(0, 320);
  cluster_arrive_relaxed();

  const int f_off = tj < 6 ? 224 * tj : 1344 + 192 * (tj - 6);
  const bool f_odd = (tj < 6) && (tj & 1);
  const int f_main = f_odd ? f_off + 32 : f_off;
  const int f_half = f_odd ? f_off : f_off + 192;
  const bool f_hashalf = tj < 6;

  if (wg == 2) {
    asm volatile("setmaxnreg.dec.sync.aligned.u32 56;");
    if (tid == 256) {
#pragma unroll
      for (int n = 1; n < 4; n++) {
        mbar_expect(bars + B_FULLB + n * 8, 30720);
        tma3d(sb + SM_B + n * 32768, &P.wq_main, bars + B_FULLB + n * 8, tj * 80, (rot + n) * 64, 0);
        mbar_expect(bars + B_FULLA + n * 8, 8192);
        tma2d(sb + SM_A + n * 8192, &P.x, bars + B_FULLA + n * 8, (rot + n) * 64, ti * 128);
        mbar_expect(bars + B_FULLA + 32 + n * 8, 8192);
        tma2d(sb + SM_A + 32768 + n * 8192, &P.x, bars + B_FULLA + 32 + n * 8, (rot + n) * 64, ti * 128 + 64);
        tma3d(sb + SM_B + n * 32768 + 24576, &P.wq_rem, bars + B_FULLB + n * 8, tj * 80 + 64, (rot + n) * 64, 0);
      }
    }
    __syncwarp();
    bar_sync(10, 128);
    unsigned* const fcol = g_fcol + tj * 160;
    unsigned* const frow = g_frow + ti * 224;
    if (w < 3 && lane != 0) return;
    if (w == 0) {
      if (lane == 0) {
        PROF(51);
#pragma unroll 1
        for (int n = 4; n < 10; n++) {
          const int s = n & 3; const uint32_t dst = sb + SM_B + s * 32768, fb = bars + B_FULLB + s * 8;
          mbar_wait(bars + B_EMPTYB + s * 8, ((n >> 2) & 1) ^ 1);
          const int k0 = (rot + n >= 10 ? rot + n - 10 : rot + n) * 64;
          mbar_expect(fb, 30720);
          tma3d(dst, &P.wq_main, fb, tj * 80, k0, 0);
          tma3d(dst + 24576, &P.wq_rem, fb, tj * 80 + 64, k0, 0);
        }
#pragma unroll 1
        for (int n = 10; n < 24; n++) {
          const int s = n & 3; const uint32_t dst = sb + SM_B + s * 32768, fb = bars + B_FULLB + s * 8;
          mbar_wait(bars + B_EMPTYB + s * 8, ((n >> 2) & 1) ^ 1);
          if (n < 14) {
            mbar_arrive(fb);
#pragma unroll 1
            for (int c = (n - 10) * 3; c < min((n - 9) * 3, 10); c++) {
              if (c > 0) mbar_wait(bars + B_WO + (c - 1) * 8, 0);
              mbar_expect(bars + B_WO + c * 8, 10240);
              tma3d(sb + SM_B + (c < 6 ? 65536 + c * 10240 : (c - 6) * 10240), &P.wo, bars + B_WO + c * 8, 0, c * 64, tj * 5);
            }
          } else {
            mbar_expect(fb, f_hashalf ? 28672 : 24576);
            const int k0 = (rot + n - 14 >= 10 ? rot + n - 24 : rot + n - 14) * 64;
            tma3d(dst, &P.w1_main, fb, 0, k0, f_main >> 6);
            if (f_hashalf) tma2d(dst + 24576, &P.w1_half, fb, f_half, k0);
          }
        }
#pragma unroll 1
        for (int t = 0; t < 10; t++) {
          const int n = 24 + t, s = n & 3;
          const bool own = (t >= 2 && !(t & 1)) || t == 9;
          const int p = own ? (t - 1) >> 1 : (t + 1) >> 1;
          mbar_wait(bars + B_EMPTYB + s * 8, ((n >> 2) & 1) ^ 1);
          mbar_expect(bars + B_FULLB + s * 8, 28672);
          tma2d(sb + SM_B + s * 32768, &P.w2, bars + B_FULLB + s * 8, (2 * p + ((tj & 1) ^ (own ? 0 : 1))) * 64, f_off);
        }
      }
    } else if (w < 3) {
      const int g = w - 1, row0 = ti * 128 + g * 64;
      const uint32_t fA = bars + B_FULLA + g * 32, eA = bars + B_EMPTYA + g * 32, dA = sb + SM_A + g * 32768;
      unsigned to = 0, th = 0;
      if (lane == 0) {
        to = next_target<8>(frow + (1 + g) * 32); th = next_target<8>(frow + (3 + g) * 32);
#pragma unroll 1
        for (int n = 4; n < 10; n++) {
          const int s = n & 3;
          mbar_wait(eA + s * 8, ((n >> 2) & 1) ^ 1);
          if (n == 9 && (to | th) == 1u) __trap();
          mbar_expect(fA + s * 8, 8192);
          tma2d(dA + s * 8192, &P.x, fA + s * 8, (rot + n >= 10 ? rot + n - 10 : rot + n) * 64, row0);
        }
        mbar_wait(bars + B_KV, 0);
        flag_wait(frow + (1 + g) * 32, to);
        fence_async_global();
        PROF(42 + g);
#pragma unroll
        for (int kc = 0; kc < 10; kc++) {
          if (kc == 4 || kc == 5) {
            const uint32_t xb = bars + B_XA + g * 16 + (kc - 4) * 8;
            if (kc == 5) mbar_wait(bars + B_XF + g * 8, 0);
            mbar_expect(xb, 8192);
            tma2d(kc == 4 ? sb + SM_B + 40960 + g * 8192 : sb + SM_X + g * 8192, &P.o64, xb, kc * 64, row0);
          } else {
            const int n = kc < 4 ? 10 + kc : 8 + kc, s = n & 3;
            mbar_wait(eA + s * 8, ((n >> 2) & 1) ^ 1);
            mbar_expect(fA + s * 8, 8192);
            tma2d(dA + s * 8192, &P.o64, fA + s * 8, kc * 64, row0);
          }
        }
        flag_wait(frow + (3 + g) * 32, th);
        fence_async_global();
        PROF(44 + g);
#pragma unroll 1
        for (int kc = 0; kc < 10; kc++) {
          const int n = 18 + kc, s = n & 3;
          mbar_wait(eA + s * 8, ((n >> 2) & 1) ^ 1);
          mbar_expect(fA + s * 8, 8192);
          tma2d(dA + s * 8192, &P.out64, fA + s * 8, (rot + kc >= 10 ? rot + kc - 10 : rot + kc) * 64, row0);
        }
        mbar_wait(fA, 0); mbar_wait(fA + 8, 0); mbar_wait(fA + 16, 0); mbar_wait(fA + 24, 0);
        flag_add(frow + 192);
      }
      cluster_wait();
      if (lane == 0) {
        int pt;
        asm volatile("ld.shared::cluster.s32 %0, [%1];" : "=r"(pt) : "r"(map_peer(bars + B_PEER, peer)) : "memory");
        if (pt != (tile ^ 1)) __trap();
        const uint32_t sf = bars + B_SF + g * 16, sr = bars + B_SR + g * 32;
        const uint32_t prf = map_peer(bars + B_RF + g * 16, peer);
        const uint32_t prb0 = map_peer(sb + SM_X + g * 8192, peer), prb1 = map_peer(dA + 24576, peer);
#pragma unroll 1
        for (int q = 0; q < 6; q++) {
          if (q < 5) {
            mbar_wait(sr + (q & 1) * 8, (q >> 1) & 1);
            fence_async_smem();
            asm volatile("cp.async.bulk.shared::cluster.shared::cta.mbarrier::complete_tx::bytes [%0], [%1], %2, [%3];" ::"r"((q & 1) ? prb1 : prb0),
                         "r"(dA + (q & 1) * 8192), "r"(8192), "r"(prf + (q & 1) * 8) : "memory");
          }
          if (q == 0) { mbar_wait(bars + B_LD, 0); continue; }
          const int p = q - 1;
          mbar_wait(sr + 16 + (p & 1) * 8, (p >> 1) & 1);
          fence_async_smem();
          tma_red2d(&P.out64, (p & 1) ? sb + SM_Y + g * 8192 : dA + 16384, (2 * p + (tj & 1)) * 64, row0);
          bulk_commit();
          if (p >= 1 && p < 4) { bulk_wait_read<1>(); mbar_arrive(sf + ((p + 1) & 1) * 8); }
        }
        bulk_wait_read<0>();
      }
    } else {
      unsigned tg[8];
      if (lane == 0) {
        if ((sb & 0xffffffu) != SB0) __trap();
        if (kMap) atomicInc(&g_started, 131);
      }
      if (lane < 30) { reinterpret_cast<uint4*>(smem + PUB_Z)[lane] = make_uint4(0, 0, 0, 0); reinterpret_cast<uint4*>(smem + PUB_Z)[lane + 30] = make_uint4(0, 0, 0, 0); }
      fence_async_smem();
      __syncwarp();
      if (lane == 0) {
        mbar_expect(bars + B_PHI, 3200);
        bulk_g2s(sb + SM_SQ, wphi + tj * 1600, 3200, bars + B_PHI);
        bulk_s2g(g_kv + tj * 3360 + ti * 208, sb + PUB_Z, ti == 15 ? 960 : 832);
        bulk_s2g(g_cs + tj * 512 + ti * 32, sb + PUB_Z, 128);
        bulk_commit();
        tg[0] = next_target<16>(fcol); tg[1] = next_target<16>(fcol + 32); tg[2] = next_target<16>(fcol + 64); tg[3] = next_target<16>(fcol + 96);
        tg[4] = next_target<16>(fcol + 128); tg[5] = next_target<8>(frow); tg[6] = next_target<16>(frow + 160); tg[7] = next_target<16>(frow + 192);
        if ((tg[0] | tg[1] | tg[2] | tg[3] | tg[4] | tg[5] | tg[6] | tg[7]) == 1u) __trap();
        bulk_wait<0>();
        flag_add(fcol + 128);
        PROF(54);
      }
      mbar_wait(bars + B_PHI, 0);
#pragma unroll 1
      for (int lc = lane; lc < 50; lc += 32) {
        const int bc = ti * 50 + lc;
        const int t = bc / 80, kg = (bc >> 3) - t * 10, nn = bc & 7, head = nn >> 1;
        const uint16_t* sphi = reinterpret_cast<const uint16_t*>(smem + SM_SQ) + head * 400 + 2 * t + (nn & 1);
        uint32_t o[4];
#pragma unroll
        for (int e = 0; e < 4; e++) {
          const int dk = kg * 8 + e * 2 - head * 20;
          const bool in = (unsigned)dk < 20u;
          const int dc = in ? dk : 0;
          const uint32_t v = (uint32_t)sphi[dc * 20] | ((uint32_t)sphi[dc * 20 + 20] << 16);
          o[e] = in ? v : 0u;
        }
        reinterpret_cast<uint4*>(smem + PUB_BD)[lc] = make_uint4(o[0], o[1], o[2], o[3]);
      }
      asm volatile("prefetch.global.L2 [%0];" ::"l"((const char*)wo + (size_t)tile * 6400 + lane * 128) : "memory");
      if (lane < 18) asm volatile("prefetch.global.L2 [%0];" ::"l"((const char*)wo + (size_t)tile * 6400 + (32 + lane) * 128) : "memory");
      fence_async_smem();
      __syncwarp();
      if (lane != 0) return;
      if (lane == 0) {
        PROF(53);
        bulk_s2g(g_bd + tj * 800 + ti * 50, sb + PUB_BD, 800);
        bulk_commit();
        bulk_wait<0>();
        flag_add(fcol);
        PROF(30);
        flag_wait(fcol + 128, tg[4]);
        fence_async_global();
      }
      bar_sync(2, 288);
      if (lane == 0) {
        fence_async_smem();
        bulk_red_f32(g_cs + tj * 512, sb + PUB_CS, 960);
        bulk_s2g(g_sq1 + (ti * 8 + tj) * 128, sb + PUB_SQ, 512);
        bulk_commit();
        bulk_wait<0>();
        flag_add(fcol + 96);
        flag_add(frow);
        PROF(52);
        flag_wait(fcol, tg[0]);
        fence_async_global();
        mbar_expect(bars + B_BD, 12800);
        bulk_g2s(sb + SM_X, g_bd + tj * 800, 12800, bars + B_BD);
        PROF(55);
        flag_wait2(frow, tg[5], fcol + 96, tg[3]);
        fence_async_global();
        mbar_expect(bars + B_CS1, 960 + 4096);
        bulk_g2s(sb + SM_CS1, g_cs + tj * 512, 960, bars + B_CS1);
        bulk_g2s(sb + SM_SQ, g_sq1 + ti * 1024, 4096, bars + B_CS1);
        PROF(31);
      }
      bar_sync(3, 288);
      if (lane == 0) {
        PROF(32);
        fence_async_smem();
        bulk_red_f32(g_kv + tj * 3360, sb + SM_KVP, 13440);
        bulk_commit();
        bulk_wait<0>();
        PROF(33);
        flag_add(fcol + 64);
      }
      bar_sync(12, 288);
      if (lane == 0) {
        flag_wait(fcol + 64, tg[2]);
        fence_async_global();
        PROF(34);
        mbar_expect(bars + B_KV, 13440);
        bulk_g2s(sb + SM_X, g_kv + tj * 3360, 13440, bars + B_KV);
      }
      bar_sync(13, 288);
      if (lane == 0) {
#pragma unroll
        for (int g = 0; g < 2; g++) {
          mbar_expect(bars + B_XR + g * 8, 10240);
          tma2d(sb + SM_X + g * 8192, &P.x, bars + B_XR + g * 8, tj * 80, ti * 128 + g * 64);
          tma2d(sb + SM_SQ + g * 2048, &P.x16, bars + B_XR + g * 8, tj * 80 + 64, ti * 128 + g * 64);
        }
        flag_wait(frow + 160, tg[6]);
        fence_async_global();
        mbar_expect(bars + B_HO, 8192);
#pragma unroll 1
        for (int q = 0; q < 8; q++) bulk_g2s(sb + SM_SQ + q * 1024, g_st2 + q * T_S + ti * 128, 1024, bars + B_HO);
      }
      bar_sync(2, 288);
      if (lane == 0) {
        fence_async_smem();
        bulk_red_f32(g_cs + tj * 512 + 256, sb + PUB_CS2, 896);
        bulk_commit();
        bulk_wait<0>();
        flag_add(fcol + 32);
        flag_wait(fcol + 32, tg[1]);
        fence_async_global();
        mbar_expect(bars + B_CS2, 896);
        bulk_g2s(sb + SM_CS2, g_cs + tj * 512 + 256, 896, bars + B_CS2);
        PROF(35);
        flag_wait(frow + 192, tg[7]);
        fence_async_global();
        mbar_arrive(bars + B_LD);
      }
    }
    if (w == 0 || w == 3) cluster_wait();
    cluster_arrive_relaxed();
    cluster_wait();
  } else {
    asm volatile("setmaxnreg.inc.sync.aligned.u32 224;");
    const bool leader = (tid & 127) == 0;
    const uint32_t abase = sb + SM_A + wg * 32768;
    const uint32_t fullA = bars + B_FULLA + wg * 32, emptyA = bars + B_EMPTYA + wg * 32;
    const int r0 = wg * 64 + w * 16 + (lane >> 2);
    const int qc = (lane & 3) * 2;
    const int hi = lane >> 4;
    const uint32_t la0 = dlo(SM_A, 16) + wg * 2048;
    const uint32_t phi_dst = abase + 11264 + (lane & 3) * 5280 + w * 256 + (lane >> 2) * 16;

    {
      *reinterpret_cast<uint4*>(smem + SM_B + (tid >> 7) * 32768 + 30720 + (tid & 127) * 16) = make_uint4(0x3f803f80u, 0x3f803f80u, 0x3f803f80u, 0x3f803f80u);
      *reinterpret_cast<uint4*>(smem + SM_B + (2 + (tid >> 7)) * 32768 + 30720 + (tid & 127) * 16) = make_uint4(0x3f803f80u, 0x3f803f80u, 0x3f803f80u, 0x3f803f80u);
      fence_async_smem();
      bar_sync(0, 320);
      float am[96], ar[28];
      float s8[8] = {0, 0, 0, 0, 0, 0, 0, 0}, q0 = 0.f, q1 = 0.f;
      uint32_t cs_a, sq_a;
      {
        const int cg = min(wid * 4 + (lane & 3), 29), rg = ((lane >> 2) & 1) * 4 + (lane >> 3), row = cs_u * 8 + rg;
        cs_a = sb + SM_B + (cg < 24 ? (cg >> 3) * 8192 + row * 128 + (((cg ^ rg) & 7) << 4) : 24576 + ((cg - 24) >> 1) * 2048 + row * 32 + (((cg ^ (rg >> 2)) & 1) << 4));
        const int r2 = w * 16 + (lane >> 1), pc = sq_v * 2 + (lane & 1);
        sq_a = abase + r2 * 128 + ((pc ^ (r2 & 7)) << 4);
      }
#pragma unroll 1
      for (int kc = 0; kc < 10; kc++) {
        const int s = kc & 3, ph_ = (kc >> 2) & 1;
        mbar_wait(fullA + s * 8, ph_);
        if (kc == 0 && tid == 0) PROF(2);
        mbar_wait(bars + B_FULLB + s * 8, ph_);
        if (kc == 0 && leader) PROF(3 + wg);
        const uint32_t la = la0 + s * 512, lb = dlo(SM_B, 8192) + s * 2048, lr = dlo(SM_B + 24576, 2048) + s * 2048;
        wg_fence();
#pragma unroll
        for (int ks = 0; ks < 4; ks++) {
          wgmma_ss_n192_t01<H128, H128>(am, la + ks * 2, lb + ks * 128, (kc | ks) != 0);
          wgmma_ss_n56_t01<H128, H32>(ar, la + ks * 2, lr + ks * 32, (kc | ks) != 0);
        }
        wg_commit();
        wg_wait<1>();
        if (kc > 0 && leader) {
          const int ps = (kc - 1) & 3;
          mbar_arrive(bars + B_EMPTYB + ps * 8);
          if (kc - 1 < 6) mbar_arrive(emptyA + ps * 8);
        }
        __syncwarp();
        if (kc < 5) {
          acc8(s8, lds16(cs_a + s * 32768));
          const uint4 v = lds16(sq_a + s * 8192);
          const uint32_t u[4] = {v.x, v.y, v.z, v.w};
#pragma unroll
          for (int e = 0; e < 4; e++) { q0 = fmaf(bf_lo(u[e]), bf_lo(u[e]), q0); q1 = fmaf(bf_hi(u[e]), bf_hi(u[e]), q1); }
        }
        if (kc == 4) {
          q0 += q1;
          q0 += __shfl_xor_sync(0xffffffffu, q0, 1);
          if ((lane & 1) == 0) reinterpret_cast<float*>(smem + PUB_SQ)[wg * 64 + w * 16 + (lane >> 1)] = q0;
        } else if (kc == 5) {
          const float t = col_reduce8(s8, lane);
          reinterpret_cast<float*>(smem + PUB_CS)[(wid * 4 + (lane & 3)) * 8 + (lane >> 2 & 1) + (lane >> 3 & 1) * 2 + (lane >> 4) * 4] = t;
          bar_arrive(2, 288);
          if (tid == 0) PROF(1);
        } else if (kc == 7) {
          if (tid < 135) {
            asm volatile("prefetch.global.L2 [%0];" ::"l"((const char*)w1 + (size_t)tile * 17280 + tid * 128) : "memory");
            asm volatile("prefetch.global.L2 [%0];" ::"l"((const char*)w2 + (size_t)tile * 17280 + tid * 128) : "memory");
          }
        }
      }
      mbar_wait(bars + B_BD, 0);
      mbar_wait(bars + B_CS1, 0);
      if (leader) PROF(57 + wg * 2);
      float sq0 = 0.f, sq1 = 0.f;
#pragma unroll
      for (int c = 0; c < 8; c++) { sq0 += reinterpret_cast<const float*>(smem + SM_SQ)[c * 128 + r0]; sq1 += reinterpret_cast<const float*>(smem + SM_SQ)[c * 128 + r0 + 8]; }
      wg_wait<0>();
      reg_fence(am); reg_fence(ar);
      if (leader) { mbar_arrive(bars + B_EMPTYB + 1 * 8); PROF(5 + wg); }
      const float nm0 = ar[24] * (-1.f / 640.f), nm1 = ar[26] * (-1.f / 640.f);
      const float rs0 = rsqrtf(fmaxf(fmaf(-nm0, nm0, sq0 * (1.f / 640.f)), 0.f) + 1e-5f), rs1 = rsqrtf(fmaxf(fmaf(-nm1, nm1, sq1 * (1.f / 640.f)), 0.f) + 1e-5f);
      const float sc0 = rs0 * 1.4426950408889634f, sc1 = rs1 * 1.4426950408889634f;
      if ((lane & 3) == 0) { reinterpret_cast<float*>(smem + SM_STP)[r0] = sc0; reinterpret_cast<float*>(smem + SM_STP)[r0 + 8] = sc1; }
      auto fold = [&](int t, uint32_t& lo, uint32_t& hi_, bool scale) {
        const float2 cs = *reinterpret_cast<const float2*>(smem + SM_CS1 + (t * 8 + qc) * 4);
        float a0 = fmaf(nm0, cs.x, t < 24 ? am[4 * t] : ar[4 * (t - 24)]), a1 = fmaf(nm0, cs.y, t < 24 ? am[4 * t + 1] : ar[4 * (t - 24) + 1]);
        float a2 = fmaf(nm1, cs.x, t < 24 ? am[4 * t + 2] : ar[4 * (t - 24) + 2]), a3 = fmaf(nm1, cs.y, t < 24 ? am[4 * t + 3] : ar[4 * (t - 24) + 3]);
        if (scale) { a0 *= rs0; a1 *= rs0; a2 *= rs1; a3 *= rs1; }
        lo = pack2(a0, a1); hi_ = pack2(a2, a3);
      };
      constexpr uint32_t dbd = dlo(SM_X, 128);
      float pp[40];
      {
        uint32_t yb[20];
#pragma unroll
        for (int t = 0; t < 10; t++) fold(t < 8 ? 8 + t : 18 + t, yb[2 * t], yb[2 * t + 1], false);
        wg_fence();
#pragma unroll
        for (int ks = 0; ks < 5; ks++) wgmma_rs_n80_t0<dhi(1280, 0)>(pp, yb[4 * ks], yb[4 * ks + 1], yb[4 * ks + 2], yb[4 * ks + 3], dbd + ks * 16, ks != 0);
        wg_commit();
        uint32_t vb[20];
#pragma unroll
        for (int t = 0; t < 10; t++) fold(t < 8 ? 16 + t : 20 + t, vb[2 * t], vb[2 * t + 1], true);
        const uint32_t stg = abase + (2 * w + ((lane >> 3) & 1)) * 128 + (lane & 7) * 16;
        stsm4(stg + (0 + hi) * 1024, vb[0], vb[1], vb[2], vb[3]);
        stsm4(stg + (2 + hi) * 1024, vb[4], vb[5], vb[6], vb[7]);
        stsm4(stg + (4 + 2 * hi) * 1024, vb[8], vb[9], vb[10], vb[11]);
        stsm4(stg + (7 + hi) * 1024, vb[12], vb[13], vb[14], vb[15]);
        stsm4(stg + (9 + hi) * 1024, vb[16], vb[17], vb[18], vb[19]);
        *reinterpret_cast<uint2*>(smem + SM_A + wg * 32768 + 5120 + (tid & 127) * 8) = make_uint2(0x3f803f80u, 0x3f803f80u);
        wg_wait<0>();
        reg_fence(pp);
      }
      if (leader) PROF(7 + wg);
      {
        const float ord = dual_softmax<0>(pp, sc0, phi_dst);
        dual_softmax<1>(pp, SWP ? fmaf(ord, 0.f, sc1) : sc1, phi_dst + 128);
      }
      fence_async_smem();
      bar_arrive(7 - wg, 256);
      bar_sync(4 + wg, 128);
      if (leader) PROF(9 + wg);
      {
        float kvd[40];
        const uint32_t rgo = dlo(SM_A, 128) + wg * 2048, rgx = dlo(SM_A + 32768, 128) - wg * 2048;
        wg_fence();
#pragma unroll
        for (int ks = 0; ks < 4; ks++) wgmma_ss_n80_t11<dhi(1024, 0), dhi(1056, 0)>(kvd, rgo + ks * 16 + wg * 320, rgo + ks * 16 + 704 + wg * 660, ks != 0);
        bar_sync(6 + wg, 256);
        wg_fence();
#pragma unroll
        for (int ks = 0; ks < 4; ks++) wgmma_ss_n80_t11<dhi(1024, 0), dhi(1056, 0)>(kvd, rgx + ks * 16 + wg * 320, rgx + ks * 16 + 704 + wg * 660, 1);
        wg_commit();
        wg_wait<0>();
        reg_fence(kvd);
        bar_arrive(9 - wg, 256);
        float* kvs = reinterpret_cast<float*>(smem + SM_KVP) + wg * 1680;
#pragma unroll
        for (int R = 0; R < 2; R++) {
          const int d = w * 16 + (lane >> 2) + 8 * R - 8 * wg;
          if ((unsigned)d < 40u) {
            const bool isB = d >= 20;
#pragma unroll
            for (int u = 0; u < 5; u++)
              *reinterpret_cast<float2*>(kvs + d * 40 + u * 8 + qc) =
                  isB ? make_float2(kvd[4 * (u + 5) + 2 * R], kvd[4 * (u + 5) + 2 * R + 1]) : make_float2(kvd[4 * u + 2 * R], kvd[4 * u + 2 * R + 1]);
          }
        }
        if ((tid & 127) >> 2 == (wg ? 0 : 16)) {
#pragma unroll
          for (int g = 0; g < 10; g++)
            *reinterpret_cast<float2*>(kvs + 1600 + g * 8 + qc) = wg ? make_float2(kvd[4 * g], kvd[4 * g + 1]) : make_float2(kvd[4 * g + 2], kvd[4 * g + 3]);
        }
        bar_arrive(3, 288);
        if (leader) PROF(11 + wg);
      }
      {
        uint32_t yb[20];
#pragma unroll
        for (int t = 0; t < 10; t++) fold(t < 8 ? t : 16 + t, yb[2 * t], yb[2 * t + 1], false);
        wg_fence();
#pragma unroll
        for (int ks = 0; ks < 5; ks++) wgmma_rs_n80_t0<dhi(1280, 0)>(pp, yb[4 * ks], yb[4 * ks + 1], yb[4 * ks + 2], yb[4 * ks + 3], dbd + ks * 16, ks != 0);
        wg_commit();
        wg_wait<0>();
        reg_fence(pp);
        bar_arrive(12, 288);
        bar_sync(8 + wg, 256);
      }
      const float sp_ = reinterpret_cast<volatile float*>(smem + SM_STP)[r0], sq_ = reinterpret_cast<volatile float*>(smem + SM_STP)[r0 + 8];
      const float ord = dual_softmax<0>(pp, sp_, phi_dst);
      dual_softmax<1>(pp, SWP ? fmaf(ord, 0.f, sq_) : sq_, phi_dst + 128);
    }
    {
      uint32_t ksrc[2], kdst[2];
      {
        const int t7 = tid & 127;
#pragma unroll
        for (int i = 0; i < 4; i++)
          if (t7 + i * 128 < 480) *reinterpret_cast<uint4*>(smem + SM_A + wg * 32768 + (t7 + i * 128) * 16) = make_uint4(0, 0, 0, 0);
#pragma unroll
        for (int i = 0; i < 2; i++) {
          const int c = min(t7 + i * 128, 239), u = c / 48, n = c - u * 48;
          const int kg = u + ((n < 40 ? n >= 20 : (n & 1)) ? 5 : 0);
          ksrc[i] = opaque(sb + SM_X + wg * 6720 + (n < 40 ? n * 160 + u * 32 : 6400 + kg * 32));
          kdst[i] = opaque(abase + (n >> 3) * 1280 + kg * 128 + (n & 7) * 16);
        }
        bar_sync(4 + wg, 128);
      }
      if (leader) PROF(13 + wg);
      mbar_wait(bars + B_KV, 0);
      if (leader) PROF(15 + wg);
      {
        const uint4 a0 = lds16(ksrc[0]), b0 = lds16(ksrc[0] + 16), a1 = lds16(ksrc[1]), b1 = lds16(ksrc[1] + 16);
        asm volatile("st.shared.v4.b32 [%0], {%1,%2,%3,%4};" ::"r"(kdst[0]), "r"(pack2(__uint_as_float(a0.x), __uint_as_float(a0.y))), "r"(pack2(__uint_as_float(a0.z), __uint_as_float(a0.w))),
                     "r"(pack2(__uint_as_float(b0.x), __uint_as_float(b0.y))), "r"(pack2(__uint_as_float(b0.z), __uint_as_float(b0.w))) : "memory");
        asm volatile("st.shared.v4.b32 [%0], {%1,%2,%3,%4};" ::"r"(kdst[1]), "r"(pack2(__uint_as_float(a1.x), __uint_as_float(a1.y))), "r"(pack2(__uint_as_float(a1.z), __uint_as_float(a1.w))),
                     "r"(pack2(__uint_as_float(b1.x), __uint_as_float(b1.y))), "r"(pack2(__uint_as_float(b1.z), __uint_as_float(b1.w))) : "memory");
      }
      if (tid == 0) PROF(56);
      fence_async_smem();
      bar_arrive(13, 288);
      bar_sync(1, 256);
      float oa0[24], oa1[24];
      {
        constexpr uint32_t d0 = dlo(SM_A, 128), d1 = dlo(SM_A + 32768, 128);
        const uint32_t a0 = dlo(SM_A + 11264, 1056) + wg * 2048, a1 = a0 + 660;
        wg_fence();
#pragma unroll
        for (int ks = 0; ks < 5; ks++) wgmma_ss_n48_t00<dhi(128, 0), dhi(1280, 0)>(oa0, a0 + ks * 132, d0 + ks * 16, ks != 0);
#pragma unroll
        for (int ks = 0; ks < 5; ks++) wgmma_ss_n48_t00<dhi(128, 0), dhi(1280, 0)>(oa1, a1 + ks * 132, d1 + ks * 16, ks != 0);
        wg_commit();
        wg_wait<0>();
        reg_fence(oa0); reg_fence(oa1);
      }
      if (tid == 0) PROF(58);
      bar_arrive(9 - wg, 256);
      bar_sync(4 + wg, 128);
      uint32_t ob[20];
#pragma unroll
      for (int pr = 0; pr < 2; pr++) {
#pragma unroll
        for (int R = 0; R < 2; R++) {
          const float dA = rcp((pr == 0 ? oa0[20 + 2 * R] : oa1[20 + 2 * R]) + 1e-6f);
          const float dB = rcp((pr == 0 ? oa0[21 + 2 * R] : oa1[21 + 2 * R]) + 1e-6f);
          const float dM = (lane & 2) ? dB : dA;
#pragma unroll
          for (int t = 0; t < 5; t++) {
            const float sc = t < 2 ? dA : (t == 2 ? dM : dB);
            const float a = pr == 0 ? oa0[4 * t + 2 * R] : oa1[4 * t + 2 * R], b = pr == 0 ? oa0[4 * t + 2 * R + 1] : oa1[4 * t + 2 * R + 1];
            ob[2 * (5 * pr + t) + R] = pack2(a * sc, b * sc);
          }
        }
      }
      stage80(abase + 12288, abase + 12288 + 8192, ob, w, lane);
      bar_sync(8 + wg, 256);
      if (leader) {
        fence_async_smem();
        PROF(17 + wg);
        tma_st2d(&P.o64, abase + 12288, tj * 80, ti * 128 + wg * 64);
        tma_st2d(&P.o16, abase + 12288 + 8192, tj * 80 + 64, ti * 128 + wg * 64);
        bulk_commit();
        bulk_wait<0>();
        flag_add(g_frow + ti * 224 + (1 + wg) * 32);
#pragma unroll
        for (int s = 0; s < 4; s++) mbar_arrive(emptyA + s * 8);
        PROF(19 + wg);
      }
      __syncwarp();
    }
    {
      float ha[40];
      {
        uint32_t xres[20];
        mbar_wait(bars + B_XR + wg * 8, 0);
        load80(sb + SM_X + wg * 8192, sb + SM_SQ + wg * 2048, xres, w, lane);
#pragma unroll
        for (int T = 0; T < 20; T++) { ha[2 * T] = bf_lo(xres[T]); ha[2 * T + 1] = bf_hi(xres[T]); }
        reg_fence(ha);
        __syncwarp();
        if (lane == 0) mbar_arrive(bars + B_XF + wg * 8);
      }
#pragma unroll
      for (int it = 0; it < 5; it++) {
        const int na = it < 2 ? 10 + 2 * it : 8 + 2 * it, sa = na & 3;
        if (it == 2) { mbar_wait(bars + B_XA + wg * 16, 0); mbar_wait(bars + B_XA + wg * 16 + 8, 0); }
        else { mbar_wait(fullA + sa * 8, (na >> 2) & 1); if (it > 0) mbar_wait(fullA + sa * 8 + 8, (na >> 2) & 1); }
        mbar_wait(bars + B_WO + (2 * it + 1) * 8, 0);
        if (it == 0 && leader) PROF(21 + wg);
        const uint32_t da0 = it == 2 ? dlo(SM_B + 40960, 16) + wg * 512 : la0 + sa * 512, da1 = it == 2 ? dlo(SM_X, 16) + wg * 512 : la0 + sa * 512 + 512;
        const uint32_t db = dlo(SM_B + (it < 3 ? 65536 + it * 20480 : (it - 3) * 20480), 2048);
        wg_fence();
#pragma unroll
        for (int ks = 0; ks < 8; ks++) {
          if (it == 0 && ks == 4) { mbar_wait(fullA + sa * 8 + 8, (na >> 2) & 1); wg_fence(); }
          wgmma_ss_n80_t01<H128, H32>(ha, (ks < 4 ? da0 : da1) + (ks & 3) * 2, db + (ks >> 2) * 640 + (ks & 3) * 32, 1);
        }
        wg_commit();
        wg_wait<0>();
        if (leader) {
          if (it == 1 || it == 2) mbar_arrive(bars + B_EMPTYB + (it + 1) * 8);
          if (it != 2) { mbar_arrive(emptyA + sa * 8); mbar_arrive(emptyA + sa * 8 + 8); }
        }
        __syncwarp();
      }
      bar_sync(4 + wg, 128);
      reg_fence(ha);
      if (leader) PROF(23 + wg);
      uint32_t hb[20];
#pragma unroll
      for (int T = 0; T < 20; T++) hb[T] = pack2(ha[2 * T], ha[2 * T + 1]);
      stage80(sb + SM_X + wg * 8192, sb + SM_SQ + wg * 2048, hb, w, lane);
      bar_sync(4 + wg, 128);
      if (tid == 0) PROF(60);
      const int row = ti * 128 + wg * 64;
      if (leader) {
        fence_async_smem();
        tma_st2d(&P.out64, sb + SM_X + wg * 8192, tj * 80, row);
        tma_st2d(&P.out16, sb + SM_SQ + wg * 2048, tj * 80 + 64, row);
        bulk_commit();
        mbar_arrive(bars + B_EMPTYB); mbar_arrive(bars + B_EMPTYB + 8);
      }
      __syncwarp();
      load80(sb + SM_X + wg * 8192, sb + SM_SQ + wg * 2048, hb, w, lane);
      float sm0 = 0.f, sm1 = 0.f;
#pragma unroll
      for (int T = 0; T < 10; T++) { sm0 += bf_lo(hb[2 * T]) + bf_hi(hb[2 * T]); sm1 += bf_lo(hb[2 * T + 1]) + bf_hi(hb[2 * T + 1]); }
      sm0 += __shfl_xor_sync(0xffffffffu, sm0, 1); sm1 += __shfl_xor_sync(0xffffffffu, sm1, 1);
      sm0 += __shfl_xor_sync(0xffffffffu, sm0, 2); sm1 += __shfl_xor_sync(0xffffffffu, sm1, 2);
      const float mu0 = sm0 * (1.f / 80.f), mu1 = sm1 * (1.f / 80.f);
      float q0 = 0.f, q1 = 0.f;
#pragma unroll
      for (int T = 0; T < 10; T++) {
        float a = bf_lo(hb[2 * T]) - mu0, b = bf_hi(hb[2 * T]) - mu0; q0 = fmaf(a, a, q0); q0 = fmaf(b, b, q0);
        a = bf_lo(hb[2 * T + 1]) - mu1; b = bf_hi(hb[2 * T + 1]) - mu1; q1 = fmaf(a, a, q1); q1 = fmaf(b, b, q1);
      }
      q0 += __shfl_xor_sync(0xffffffffu, q0, 1); q1 += __shfl_xor_sync(0xffffffffu, q1, 1);
      q0 += __shfl_xor_sync(0xffffffffu, q0, 2); q1 += __shfl_xor_sync(0xffffffffu, q1, 2);
      if ((lane & 3) == 0) {
        reinterpret_cast<float2*>(smem + SM_STP)[r0] = make_float2(sm0, q0);
        reinterpret_cast<float2*>(smem + SM_STP)[r0 + 8] = make_float2(sm1, q1);
      }
      bar_sync(4 + wg, 128);
      if (leader) {
        bulk_wait<0>();
        flag_add(g_frow + ti * 224 + (3 + wg) * 32);
        PROF(25 + wg);
        fence_async_smem();
        bulk_s2g(g_st2 + tj * T_S + row, sb + SM_STP + wg * 512, 512);
        bulk_commit();
        bulk_wait<0>();
        flag_add(g_frow + ti * 224 + 160);
      }
      __syncwarp();
    }
    const uint32_t rowA = dlo(SM_B, 16) + (f_odd ? 256 : 0), rowB = dlo(SM_B, 16) + (f_odd ? 0 : 1536);
    const int srow = w * 16 + ((lane >> 3) & 1) * 8 + (lane & 7);
    uint32_t sa_[4];
#pragma unroll
    for (int i = 0; i < 4; i++) {
      const uint32_t o = srow * 128 + (((2 * i + hi) ^ (srow & 7)) << 4);
      sa_[i] = opaque(abase + o);
    }
    const uint32_t bb = opaque(bars), bw = opaque(bars + wg * 16), bw4 = opaque(bars + wg * 32);
    const uint32_t pre = map_peer(bars + B_RE + wg * 16, peer);
    const int turn = opaque(8 + wg), next = opaque(9 - wg);
    const bool l0 = opaque(lane) == 0, ld = opaque(tid & 127) == 0;
    const uint32_t yoff = opaque(SM_Y - SM_A - wg * 24576);
    uint32_t idf[16];
    {
      const uint32_t e = (lane >> 2) == qc ? 0x00003f80u : ((lane >> 2) == qc + 1 ? 0x3f800000u : 0u);
#pragma unroll
      for (int i = 0; i < 16; i++) idf[i] = opaque(((i >> 2) == w && ((i & 3) == 0 || (i & 3) == 3)) ? e : 0u);
    }
    const uint32_t rd0 = dlo(SM_X, 16) + wg * 512, rd1 = dlo(SM_A + 24576, 16) + wg * 2048;
    cluster_wait();
    uint32_t af[56];
    {
      float fa[112];
      float s8[8] = {0, 0, 0, 0, 0, 0, 0, 0};
      uint32_t cs_a;
      {
        const int cg = min(wid * 4 + (lane & 3), 27), rg = ((lane >> 2) & 1) * 4 + (lane >> 3);
        cs_a = sb + SM_B + (cg >> 3) * 8192 + (cs_u * 8 + rg) * 128 + (((cg ^ rg) & 7) << 4);
      }
#pragma unroll 1
      for (int kc = 0; kc < 10; kc++) {
        const int na = 18 + kc, sa = na & 3, nb = 14 + kc, sbk = nb & 3;
        mbar_wait(fullA + sa * 8, (na >> 2) & 1);
        mbar_wait(bars + B_FULLB + sbk * 8, (nb >> 2) & 1);
        if (kc == 0 && leader) PROF(27 + wg);
        const uint32_t da = la0 + sa * 512, db = dlo(SM_B, 8192) + sbk * 2048;
        wg_fence();
#pragma unroll
        for (int ks = 0; ks < 4; ks++) wgmma_ss_n224_t01<H128, H128>(fa, da + ks * 2, db + ks * 128, (kc | ks) != 0);
        wg_commit();
        wg_wait<1>();
        if (kc > 0 && leader) {
          mbar_arrive(bars + B_EMPTYB + ((nb - 1) & 3) * 8);
          if (kc - 1 < 6) mbar_arrive(emptyA + ((na - 1) & 3) * 8);
        }
        __syncwarp();
        if (kc < 5) {
          acc8(s8, lds16(cs_a + sbk * 32768));
        } else if (kc == 5) {
          const float t = col_reduce8(s8, lane);
          if (wid < 7) reinterpret_cast<float*>(smem + PUB_CS2)[(wid * 4 + (lane & 3)) * 8 + (lane >> 2 & 1) + (lane >> 3 & 1) * 2 + (lane >> 4) * 4] = t;
          bar_arrive(2, 288);
        }
      }
      mbar_wait(bars + B_HO, 0);
      const float2* sq = reinterpret_cast<const float2*>(smem + SM_SQ) + qc * 128 + r0;
      const float2 sp[4] = {sq[0], sq[128], sq[8], sq[136]};
      float m0 = sp[0].x + sp[1].x, m1 = sp[2].x + sp[3].x;
      m0 += __shfl_xor_sync(0xffffffffu, m0, 1); m1 += __shfl_xor_sync(0xffffffffu, m1, 1);
      m0 += __shfl_xor_sync(0xffffffffu, m0, 2); m1 += __shfl_xor_sync(0xffffffffu, m1, 2);
      m0 *= (1.f / 640.f); m1 *= (1.f / 640.f);
      const float e0 = sp[0].x * (1.f / 80.f) - m0, e1 = sp[1].x * (1.f / 80.f) - m0, e2 = sp[2].x * (1.f / 80.f) - m1, e3 = sp[3].x * (1.f / 80.f) - m1;
      float v0 = sp[0].y + sp[1].y + 80.f * (e0 * e0 + e1 * e1), v1 = sp[2].y + sp[3].y + 80.f * (e2 * e2 + e3 * e3);
      v0 += __shfl_xor_sync(0xffffffffu, v0, 1); v1 += __shfl_xor_sync(0xffffffffu, v1, 1);
      v0 += __shfl_xor_sync(0xffffffffu, v0, 2); v1 += __shfl_xor_sync(0xffffffffu, v1, 2);
      const float rs0 = rsqrtf(v0 * (1.f / 640.f) + 1e-5f), rs1 = rsqrtf(v1 * (1.f / 640.f) + 1e-5f);
      mbar_wait(bars + B_CS2, 0);
      wg_wait<0>();
      reg_fence(fa);
      if (leader) { mbar_arrive(bars + B_EMPTYB + (23 & 3) * 8); PROF(36 + wg); }
      m0 *= -rs0; m1 *= -rs1;
#pragma unroll
      for (int t = 0; t < 28; t++) {
        const float2 cs = *reinterpret_cast<const float2*>(smem + SM_CS2 + (t * 8 + qc) * 4);
        uint32_t u0 = pack2_relu(fmaf(fa[4 * t], rs0, m0 * cs.x), fmaf(fa[4 * t + 1], rs0, m0 * cs.y));
        uint32_t u1 = pack2_relu(fmaf(fa[4 * t + 2], rs1, m1 * cs.x), fmaf(fa[4 * t + 3], rs1, m1 * cs.y));
        if (t >= 24 && !f_hashalf) { u0 = 0; u1 = 0; }
        af[2 * t] = u0; af[2 * t + 1] = u1;
      }
    }
    {
      auto send = [&](const float* oc, int sl) {
#pragma unroll
        for (int i = 0; i < 4; i++)
          stsm4(sa_[i] + (sl == 3 ? yoff : sl * 8192), pack2(oc[8 * i], oc[8 * i + 1]), pack2(oc[8 * i + 2], oc[8 * i + 3]), pack2(oc[8 * i + 4], oc[8 * i + 5]), pack2(oc[8 * i + 6], oc[8 * i + 7]));
        __syncwarp();
        if (l0) mbar_arrive(bw4 + B_SR + sl * 8);
      };
      bar_arrive(7 - wg, 256);
      bar_sync(4 + wg, 128);
      if (ld) {
        mbar_expect(bw + B_RF, 8192); mbar_expect(bw + B_RF + 8, 8192);
        PROF(38 + wg);
      }
      if (l0) {
        asm volatile("mbarrier.arrive.shared::cluster.b64 _, [%0];" ::"r"(pre) : "memory");
        asm volatile("mbarrier.arrive.shared::cluster.b64 _, [%0];" ::"r"(pre + 8) : "memory");
      }
      __syncwarp();
      {
        float oc[32];
        mbar_wait(bb + B_FULLB, 0);
        if (wg) bar_sync(turn, 256);
        wg_fence();
#pragma unroll
        for (int ks = 0; ks < 14; ks++)
          wgmma_rs_n64_t1<H128>(oc, af[4 * ks], af[4 * ks + 1], af[4 * ks + 2], af[4 * ks + 3], (ks < 12 ? rowA + ks * 128 : rowB + (ks - 12) * 128), ks != 0);
        wg_commit();
        bar_arrive(next, 256);
        mbar_wait(bw + B_RE, 0);
        wg_wait<0>();
        reg_fence(oc);
        if (ld) mbar_arrive(bb + B_EMPTYB);
        send(oc, 0);
      }
#pragma unroll UNR
      for (int q = 1; q < 5; q++) {
        float os[32], oo[32];
        const int s = (23 + 2 * q) & 3, s2 = (24 + 2 * q) & 3;
        mbar_wait(bb + B_FULLB + s * 8, ((23 + 2 * q) >> 2) & 1);
        mbar_wait(bb + B_FULLB + s2 * 8, ((24 + 2 * q) >> 2) & 1);
        bar_sync(turn, 256);
        wg_fence();
#pragma unroll
        for (int ks = 0; ks < 14; ks++)
          wgmma_rs_n64_t1<H128>(os, af[4 * ks], af[4 * ks + 1], af[4 * ks + 2], af[4 * ks + 3], (ks < 12 ? rowA + ks * 128 : rowB + (ks - 12) * 128) + s * 2048, ks != 0);
#pragma unroll
        for (int ks = 0; ks < 14; ks++)
          wgmma_rs_n64_t1<H128>(oo, af[4 * ks], af[4 * ks + 1], af[4 * ks + 2], af[4 * ks + 3], (ks < 12 ? rowA + ks * 128 : rowB + (ks - 12) * 128) + s2 * 2048, ks != 0);
        mbar_wait(bw + B_RF + ((q - 1) & 1) * 8, ((q - 1) >> 1) & 1);
        wg_fence();
#pragma unroll
        for (int ks = 0; ks < 4; ks++) wgmma_rs_n64_t1<H128>(oo, idf[4 * ks], idf[4 * ks + 1], idf[4 * ks + 2], idf[4 * ks + 3], ((q & 1) ? rd0 : rd1) + ks * 128, 1);
        wg_commit();
        bar_arrive(next, 256);
        if (q < 4 && ld) mbar_expect(bw + B_RF + ((q - 1) & 1) * 8, 8192);
        mbar_wait(bw + B_RE + (q & 1) * 8, (q >> 1) & 1);
        if (q == 2) bar_sync(6 + wg, 256);
        if (q >= 3) mbar_wait(bw + B_SF + ((q - 1) & 1) * 8, 0);
        wg_wait<0>();
        reg_fence(os); reg_fence(oo);
        if (ld) { mbar_arrive(bb + B_EMPTYB + s * 8); mbar_arrive(bb + B_EMPTYB + s2 * 8); }
        if (q < 4 && l0) asm volatile("mbarrier.arrive.shared::cluster.b64 _, [%0];" ::"r"(pre + ((q - 1) & 1) * 8) : "memory");
        send(os, q & 1);
        send(oo, 2 + ((q - 1) & 1));
      }
      {
        float oc[32];
        mbar_wait(bb + B_FULLB + 8, 0);
        bar_sync(turn, 256);
        wg_fence();
#pragma unroll
        for (int ks = 0; ks < 14; ks++)
          wgmma_rs_n64_t1<H128>(oc, af[4 * ks], af[4 * ks + 1], af[4 * ks + 2], af[4 * ks + 3], (ks < 12 ? rowA + ks * 128 : rowB + (ks - 12) * 128) + 2048, ks != 0);
        if (!wg) bar_arrive(next, 256);
        mbar_wait(bw + B_RF, 0);
        wg_fence();
#pragma unroll
        for (int ks = 0; ks < 4; ks++) wgmma_rs_n64_t1<H128>(oc, idf[4 * ks], idf[4 * ks + 1], idf[4 * ks + 2], idf[4 * ks + 3], rd0 + ks * 128, 1);
        wg_commit();
        mbar_wait(bw + B_SF, 1);
        wg_wait<0>();
        reg_fence(oc);
        send(oc, 2);
      }
      if (leader) PROF(46 + wg);
      cluster_arrive_relaxed();
      cluster_wait();
      if (leader) PROF(48 + wg);
    }
  }
}

typedef CUresult (*EncFn)(CUtensorMap*, CUtensorMapDataType, cuuint32_t, void*, const cuuint64_t*, const cuuint64_t*, const cuuint32_t*,
                          const cuuint32_t*, CUtensorMapInterleave, CUtensorMapSwizzle, CUtensorMapL2promotion, CUtensorMapFloatOOBfill);

void enc_map(EncFn enc, CUtensorMap* m, const void* p, int rank, const uint64_t* dims, const uint64_t* strides, const uint32_t* box, CUtensorMapSwizzle sw) {
  cuuint64_t d[3], s[2]; cuuint32_t b[3], e[3] = {1, 1, 1};
  for (int i = 0; i < rank; i++) { d[i] = dims[i]; b[i] = box[i]; }
  for (int i = 0; i < rank - 1; i++) s[i] = strides[i];
  enc(m, CU_TENSOR_MAP_DATA_TYPE_BFLOAT16, rank, const_cast<void*>(p), d, s, b, e, CU_TENSOR_MAP_INTERLEAVE_NONE, sw,
      CU_TENSOR_MAP_L2_PROMOTION_L2_256B, CU_TENSOR_MAP_FLOAT_OOB_FILL_NONE);
}
void enc2(EncFn enc, CUtensorMap* m, const void* p, uint64_t d0, uint64_t d1, uint32_t b0, uint32_t b1, CUtensorMapSwizzle sw) {
  const uint64_t d[2] = {d0, d1}, s[1] = {d0 * 2}; const uint32_t b[2] = {b0, b1};
  enc_map(enc, m, p, 2, d, s, b, sw);
}
void enc3(EncFn enc, CUtensorMap* m, const void* p, uint64_t d0, uint64_t d1, uint64_t d2, uint64_t s1, uint64_t s2, uint32_t b0, uint32_t b1, uint32_t b2, CUtensorMapSwizzle sw) {
  const uint64_t d[3] = {d0, d1, d2}, s[2] = {s1, s2}; const uint32_t b[3] = {b0, b1, b2};
  enc_map(enc, m, p, 3, d, s, b, sw);
}

}

extern "C" void kernel_launch(void* const* d_in, const int* in_sizes, int n_in, void* d_out, int out_size) {
  (void)in_sizes; (void)n_in; (void)out_size;
  const __nv_bfloat16* x = (const __nv_bfloat16*)d_in[0];
  const __nv_bfloat16* wqkv = (const __nv_bfloat16*)d_in[1];
  const __nv_bfloat16* wphi = (const __nv_bfloat16*)d_in[2];
  const __nv_bfloat16* wo = (const __nv_bfloat16*)d_in[3];
  const __nv_bfloat16* w1 = (const __nv_bfloat16*)d_in[5];
  const __nv_bfloat16* w2 = (const __nv_bfloat16*)d_in[6];

  static EncFn enc = nullptr;
  static bool use_map = false;
  static void* po = nullptr;
  if (!enc) {
    void* fn = nullptr; cudaDriverEntryPointQueryResult qr;
    cudaGetDriverEntryPoint("cuTensorMapEncodeTiled", &fn, cudaEnableDefault, &qr);
    enc = (EncFn)fn;
    cudaFuncSetAttribute(fused_block_kernel<true>, cudaFuncAttributeMaxDynamicSharedMemorySize, SM_TOTAL);
    cudaFuncSetAttribute(fused_block_kernel<false>, cudaFuncAttributeMaxDynamicSharedMemorySize, SM_TOTAL);
    cudaGetSymbolAddress(&po, g_o);
    int dev = 0, sms = 0; cudaGetDevice(&dev); cudaDeviceGetAttribute(&sms, cudaDevAttrMultiProcessorCount, dev);
    cudaLaunchConfig_t cfg = {}; cfg.gridDim = dim3(128); cfg.blockDim = dim3(384); cfg.dynamicSmemBytes = SM_TOTAL;
    cudaLaunchAttribute at[1]; at[0].id = cudaLaunchAttributeClusterDimension; at[0].val.clusterDim.x = 8; at[0].val.clusterDim.y = 1; at[0].val.clusterDim.z = 1;
    cfg.attrs = at; cfg.numAttrs = 1;
    int n8 = 0;
    if (cudaOccupancyMaxActiveClusters(&n8, fused_block_kernel<false>, &cfg) != cudaSuccess) { n8 = 0; (void)cudaGetLastError(); }
    use_map = (sms == 132 && n8 == 15);
  }
  Params P;
  const CUtensorMapSwizzle S128 = CU_TENSOR_MAP_SWIZZLE_128B, S32 = CU_TENSOR_MAP_SWIZZLE_32B;
  enc2(enc, &P.x, x, 640, 2048, 64, 64, S128);
  enc2(enc, &P.x16, x, 640, 2048, 16, 64, S32);
  enc3(enc, &P.wq_main, wqkv, 640, 640, 3, 3840, 1280, 64, 64, 3, S128);
  enc3(enc, &P.wq_rem, wqkv, 640, 640, 3, 3840, 1280, 16, 64, 3, S32);
  enc2(enc, &P.o64, po, 640, 2048, 64, 64, S128);
  enc2(enc, &P.o16, po, 640, 2048, 16, 64, S32);
  enc3(enc, &P.wo, wo, 16, 640, 40, 1280, 32, 16, 64, 5, S32);
  enc2(enc, &P.out64, d_out, 640, 2048, 64, 64, S128);
  enc2(enc, &P.out16, d_out, 640, 2048, 16, 64, S32);
  enc3(enc, &P.w1_main, w1, 64, 640, 27, 3456, 128, 64, 64, 3, S128);
  enc2(enc, &P.w1_half, w1, 1728, 640, 32, 64, S128);
  enc2(enc, &P.w2, w2, 640, 1728, 64, 224, S128);
  cudaLaunchConfig_t cfg = {};
  cfg.gridDim = dim3(use_map ? 132 : 128); cfg.blockDim = dim3(384); cfg.dynamicSmemBytes = SM_TOTAL; cfg.stream = cudaStreamPerThread;
  cudaLaunchAttribute at[1];
  at[0].id = cudaLaunchAttributeClusterDimension; at[0].val.clusterDim.x = 2; at[0].val.clusterDim.y = 1; at[0].val.clusterDim.z = 1;
  cfg.attrs = at; cfg.numAttrs = 1;
  cudaLaunchKernelEx(&cfg, use_map ? fused_block_kernel<true> : fused_block_kernel<false>, P, wphi, wo, w1, w2);
}
```
